```python
import torch

def _softmax(x, axis=-1):
    return torch.softmax(x, dim=axis)
def _gelu(x):
    return torch.nn.functional.gelu(x, approximate="tanh")
def _silu(x):
    return torch.nn.functional.silu(x)
def _sigmoid(x):
    return torch.sigmoid(x)
def _layernorm(x, axis=-1, eps=1e-5):
    m = x.mean(dim=axis, keepdim=True)
    v = x.var(dim=axis, keepdim=True, unbiased=False)
    return (x - m) / torch.sqrt(v + eps)
def _scatter_add(tgt, idx, src, axis=0):
    return tgt.clone().index_add_(axis, idx, src)
def _segment_sum(src, seg, n):
    out = torch.zeros((n,) + src.shape[1:], dtype=src.dtype)
    return out.index_add_(0, seg, src)
def _pad(x, pw):
    flat = tuple(v for pair in reversed(pw) for v in pair)
    return torch.nn.functional.pad(x, flat)

kernel_name = 'parallel_sum__sliding_local_dilated__dense_activation_squared_relu__prompt'

def setup_inputs():

    _w = (lambda a: (lambda t: t.to(torch.bfloat16) if t.is_floating_point() else t)(torch.as_tensor(a)))
    def _A_setup():
        B, S, D = 1, 2048, 576
        return {
            "x": _w((lambda *s: torch.randn(*s, dtype=torch.bfloat16) * 0.05)(B, S, D)),
            "wqkv": _w((lambda *s: torch.randn(*s, dtype=torch.bfloat16) * 0.1)(D, 3 * D)),
            "wo": _w((lambda *s: torch.randn(*s, dtype=torch.bfloat16) * 0.05)(D, D)),
        }
    _A_in = _A_setup()

    def _B_setup():
        B, S, D, F = 1, 2048, 576, 4608
        return {
            "x": _w((lambda *s: torch.randn(*s, dtype=torch.bfloat16) * 0.05)(B, S, D)),
            "w1": _w((lambda *s: torch.randn(*s, dtype=torch.bfloat16) * 0.05)(D, F)),
            "b1": _w((lambda *s: torch.randn(*s, dtype=torch.bfloat16) * 0.2)(F)),
            "w2": _w((lambda *s: torch.randn(*s, dtype=torch.bfloat16) * 0.05)(F, D)),
            "b2": _w((lambda *s: torch.randn(*s, dtype=torch.bfloat16) * 1.6)(D)),
        }
    _B_in = _B_setup()

    return {
        "A_x": _A_in["x"],
        "A_wqkv": _A_in["wqkv"],
        "A_wo": _A_in["wo"],
        "B_x": _B_in["x"],
        "B_w1": _B_in["w1"],
        "B_b1": _B_in["b1"],
        "B_w2": _B_in["w2"],
        "B_b2": _B_in["b2"],
    }

def reference(A_x, A_wqkv, A_wo, B_x, B_w1, B_b1, B_w2, B_b2):
    def _A_ref(x, wqkv, wo):
        B, S, D = x.shape
        H = 32; Dh = D // H
        W, dil = 8, 2
        qkv = (lambda x, *d: x.permute(*d))((x @ wqkv).reshape(B, S, 3, H, Dh), 2, 0, 3, 1, 4)
        q, k, v = qkv[0], qkv[1], qkv[2]
        scale = Dh ** -0.5
        pos = torch.arange(S)
        off = torch.arange(W) * dil
        idx = pos[:, None] - off[None, :]
        mask = idx >= 0
        idx_c = torch.where(mask, idx, 0).reshape(-1)
        kg = k[:, :, idx_c, :].reshape(B, H, S, W, Dh)
        vg = v[:, :, idx_c, :].reshape(B, H, S, W, Dh)
        logits = torch.einsum("bhsd,bhswd->bhsw", q, kg) * scale
        logits = torch.where(mask[None, None, :, :], logits, -1e9)
        attn = _softmax(logits, axis=-1)
        o = torch.einsum("bhsw,bhswd->bhsd", attn, vg)
        return (lambda x, *d: x.permute(*d))(o, 0, 2, 1, 3).reshape(B, S, D) @ wo

    def _B_ref(x, w1, b1, w2, b2):
        h = torch.einsum("bsd,df->bsf", x, w1) + b1
        zero = torch.zeros_like(h)
        r = torch.where(h > zero, h, zero)
        h = r * r
        out = torch.einsum("bsf,fd->bsd", h, w2) + b2
        return out

    x = A_x
    xn = _layernorm(x, axis=-1)
    return x + _A_ref(xn, A_wqkv, A_wo) + _B_ref(xn, B_w1, B_b1, B_w2, B_b2)
```

```cpp
#include <cuda_runtime.h>
#include <cuda_bf16.h>
#include <cuda.h>
#include <stdint.h>
#include <type_traits>

namespace {

constexpr uint32_t O_OFF    = 0;
constexpr uint32_t SP2_OFF  = 20480;
constexpr uint32_t H_OFF    = 24576;
constexpr uint32_t HSLOT    = 24576;
constexpr uint32_t RING_OFF = 147456;
constexpr uint32_t B1_OFF   = RING_OFF + 6 * 12288;
constexpr uint32_t BAR_OFF  = B1_OFF + 1152;
constexpr uint32_t SP_OFF   = BAR_OFF + 896;
constexpr uint32_t SMEM_BYTES = 232448;
__host__ __device__ constexpr uint32_t G2S(int k) {
  return k < 6 ? RING_OFF + ((3 + k) % 6) * 12288 : H_OFF + 2 * HSLOT + (k - 6) * 12288;
}
__device__ __forceinline__ constexpr uint32_t KST(int t) { return t < 6 ? H_OFF + (3 + t / 3) * HSLOT + 8192 + (t % 3) * 5376 : SP_OFF + (t - 6) * 5376; }
__device__ __forceinline__ constexpr uint32_t VST(int t) { return t < 7 ? KST(t) + 2688 : SP2_OFF; }
constexpr int F1 = 0, FG = 6, E1 = 16, EG = 22, B_HFREE = 32, B_B1 = 33, B_QS = 34, B_O = 37, B_STG = 40, B_RED = 43, B_RFREE = 45, B_B2 = 46, B_X = 47;

constexpr int LAG = 2, LAG2 = 5;
constexpr int DEFK = 3;
constexpr int QPACE = 100, RPACE = 100;

__device__ __align__(1024) uint32_t g_qkvT[864 * 2 * 1024];
__device__ unsigned int g_cnt[16 * 32];
__device__ unsigned int g_used[16 * 32];

__device__ __forceinline__ uint32_t s2u(const void* p) { return (uint32_t)__cvta_generic_to_shared(p); }
__device__ __forceinline__ void mbar_init(uint32_t b, uint32_t c) { asm volatile("mbarrier.init.shared::cta.b64 [%0], %1;" :: "r"(b), "r"(c)); }
__device__ __forceinline__ void mbar_expect(uint32_t b, uint32_t bytes) { asm volatile("mbarrier.arrive.expect_tx.shared::cta.b64 _, [%0], %1;" :: "r"(b), "r"(bytes) : "memory"); }
__device__ __forceinline__ void mbar_arrive(uint32_t b) { asm volatile("mbarrier.arrive.shared::cta.b64 _, [%0];" :: "r"(b) : "memory"); }
__device__ __forceinline__ void mbar_wait(uint32_t b, uint32_t ph) {
  asm volatile(
    "{\n.reg .pred p;\n.reg .u32 n;\nmov.u32 n, 0;\n"
    "W_L:\n"
    "mbarrier.try_wait.parity.shared::cta.b64 p, [%0], %1;\n"
    "@p bra D_L;\n"
    "add.u32 n, n, 1;\n"
    "setp.lt.u32 p, n, 4000000;\n"
    "@p bra W_L;\n"
    "trap;\n"
    "D_L:\n}\n" :: "r"(b), "r"(ph) : "memory");
}
__device__ __forceinline__ void mbar_wait_c(uint32_t b, uint32_t ph) {
  asm volatile("{\n.reg .pred p;\nW_L:\nmbarrier.try_wait.parity.shared::cta.b64 p, [%0], %1;\n@!p bra W_L;\n}\n" :: "r"(b), "r"(ph) : "memory");
}
__device__ __forceinline__ uint32_t mbar_peek(uint32_t b, uint32_t ph) {
  uint32_t ok;
  asm volatile("{\n.reg .pred p;\nmbarrier.try_wait.parity.shared::cta.b64 p, [%1], %2;\nselp.u32 %0, 1, 0, p;\n}\n" : "=r"(ok) : "r"(b), "r"(ph) : "memory");
  return ok;
}
__device__ __forceinline__ bool elect_one() {
  uint32_t p; asm volatile("{\n.reg .pred P;\nelect.sync _|P, 0xffffffff;\nselp.u32 %0, 1, 0, P;\n}\n" : "=r"(p)); return p;
}
__device__ __forceinline__ void tma3d_mc(uint32_t dst, const CUtensorMap* tm, int c0, int c1, int c2, uint32_t bar) {
  asm volatile("cp.async.bulk.tensor.3d.shared::cluster.global.mbarrier::complete_tx::bytes.multicast::cluster [%0], [%1, {%3, %4, %5}], [%2], %6;"
    :: "r"(dst), "l"(tm), "r"(bar), "r"(c0), "r"(c1), "r"(c2), "h"((uint16_t)3) : "memory");
}
__device__ __forceinline__ void tma4d(uint32_t dst, const CUtensorMap* tm, int c0, int c1, int c2, int c3, uint32_t bar) {
  asm volatile("cp.async.bulk.tensor.4d.shared::cluster.global.mbarrier::complete_tx::bytes [%0], [%1, {%3, %4, %5, %6}], [%2];"
    :: "r"(dst), "l"(tm), "r"(bar), "r"(c0), "r"(c1), "r"(c2), "r"(c3) : "memory");
}
__device__ __forceinline__ void tma3d(uint32_t dst, const CUtensorMap* tm, int c0, int c1, int c2, uint32_t bar) {
  asm volatile("cp.async.bulk.tensor.3d.shared::cluster.global.mbarrier::complete_tx::bytes [%0], [%1, {%3, %4, %5}], [%2];"
    :: "r"(dst), "l"(tm), "r"(bar), "r"(c0), "r"(c1), "r"(c2) : "memory");
}
__device__ __forceinline__ void tma_st4d(const CUtensorMap* tm, int c0, int c1, int c2, int c3, uint32_t src) {
  asm volatile("cp.async.bulk.tensor.4d.global.shared::cta.tile.bulk_group [%0, {%2, %3, %4, %5}], [%1];"
    :: "l"(tm), "r"(src), "r"(c0), "r"(c1), "r"(c2), "r"(c3) : "memory");
}
__device__ __forceinline__ void bulk_commit() { asm volatile("cp.async.bulk.commit_group;" ::: "memory"); }
__device__ __forceinline__ uint2 lds64(uint32_t a) {
  uint2 v; asm volatile("ld.shared.v2.u32 {%0,%1}, [%2];" : "=r"(v.x), "=r"(v.y) : "r"(a) : "memory"); return v;
}
__device__ __forceinline__ void ldsm4(uint32_t a, uint32_t& r0, uint32_t& r1, uint32_t& r2, uint32_t& r3) {
  asm volatile("ldmatrix.sync.aligned.m8n8.x4.shared.b16 {%0,%1,%2,%3}, [%4];" : "=r"(r0), "=r"(r1), "=r"(r2), "=r"(r3) : "r"(a) : "memory");
}
__device__ __forceinline__ uint32_t mapa(uint32_t a, uint32_t cta) {
  uint32_t r; asm volatile("mapa.shared::cluster.u32 %0, %1, %2;" : "=r"(r) : "r"(a), "r"(cta)); return r;
}
__device__ __forceinline__ void arrive_cluster(uint32_t ra) {
  asm volatile("mbarrier.arrive.shared::cluster.b64 _, [%0];" :: "r"(ra) : "memory");
}
__device__ __forceinline__ uint4 lds128(uint32_t a) {
  uint4 v; asm volatile("ld.shared.v4.u32 {%0,%1,%2,%3}, [%4];" : "=r"(v.x), "=r"(v.y), "=r"(v.z), "=r"(v.w) : "r"(a) : "memory"); return v;
}
__device__ __forceinline__ void tma_red4d(const CUtensorMap* tm, int c0, int c1, int c2, int c3, uint32_t src) {
  asm volatile("cp.reduce.async.bulk.tensor.4d.global.shared::cta.add.tile.bulk_group [%0, {%2, %3, %4, %5}], [%1];"
    :: "l"(tm), "r"(src), "r"(c0), "r"(c1), "r"(c2), "r"(c3) : "memory");
}
__device__ __forceinline__ void l2_prefetch(const void* p, uint32_t bytes) {
  asm volatile("cp.async.bulk.prefetch.L2.global [%0], %1;" :: "l"(p), "r"(bytes) : "memory");
}
__device__ __forceinline__ void pf_l2(const void* p) { asm volatile("prefetch.global.L2 [%0];" :: "l"(p) : "memory"); }
template <int ROWS, int BYTES> __device__ __forceinline__ void pf_rows(const void* base, size_t pitch, int ht) {
  constexpr int G = BYTES / 64;
#pragma unroll
  for (int e = ht; e < ROWS * G; e += 96) pf_l2((const uint8_t*)base + (size_t)(e / G) * pitch + (e % G) * 64);
}
__device__ __forceinline__ void wg_arrive() { asm volatile("wgmma.fence.sync.aligned;" ::: "memory"); }
__device__ __forceinline__ void wg_commit() { asm volatile("wgmma.commit_group.sync.aligned;" ::: "memory"); }
template <int N> __device__ __forceinline__ void wg_wait() { asm volatile("wgmma.wait_group.sync.aligned %0;" :: "n"(N) : "memory"); }
template <int N> __device__ __forceinline__ void fence_regs(float (&d)[N]) {
#pragma unroll
  for (int i = 0; i < N; i++) asm volatile("" : "+f"(d[i]) :: "memory");
}
__device__ __forceinline__ uint32_t pack_bf16(float lo, float hi) {
  uint32_t r; asm("cvt.rn.bf16x2.f32 %0, %1, %2;" : "=r"(r) : "f"(hi), "f"(lo)); return r;
}
__device__ __forceinline__ float sqrt_fast(float x) { float r; asm("sqrt.approx.f32 %0, %1;" : "=f"(r) : "f"(x)); return r; }
__device__ __forceinline__ float ex2(float x) { float r; asm("ex2.approx.ftz.f32 %0, %1;" : "=f"(r) : "f"(x)); return r; }
__device__ __forceinline__ uint32_t bf2_sq(uint32_t a) { uint32_t r; asm("mul.rn.bf16x2 %0, %1, %1;" : "=r"(r) : "r"(a)); return r; }
__device__ __forceinline__ uint32_t bf2_fma(uint32_t a, uint32_t b, uint32_t c) { uint32_t r; asm("fma.rn.bf16x2 %0, %1, %2, %3;" : "=r"(r) : "r"(a), "r"(b), "r"(c)); return r; }
__device__ __forceinline__ uint32_t bf2_add_relu(uint32_t a, uint32_t c) { uint32_t r; asm("fma.rn.relu.bf16x2 %0, %1, %2, %3;" : "=r"(r) : "r"(a), "r"(0x3f803f80u), "r"(c)); return r; }
__device__ __forceinline__ uint32_t bf2_mul(uint32_t a, uint32_t b) { uint32_t r; asm("mul.rn.bf16x2 %0, %1, %2;" : "=r"(r) : "r"(a), "r"(b)); return r; }
__device__ __forceinline__ uint32_t bf2_sub(uint32_t a, uint32_t b) { uint32_t r; asm("sub.rn.bf16x2 %0, %1, %2;" : "=r"(r) : "r"(a), "r"(b)); return r; }
__device__ __forceinline__ uint32_t bf2_add(uint32_t a, uint32_t b) { uint32_t r; asm("add.rn.bf16x2 %0, %1, %2;" : "=r"(r) : "r"(a), "r"(b)); return r; }
__device__ __forceinline__ float bf_lo(uint32_t v) { return __uint_as_float(v << 16); }
__device__ __forceinline__ float bf_hi(uint32_t v) { return __uint_as_float(v & 0xffff0000u); }
__device__ __forceinline__ void mma16816(float (&d)[4], uint32_t a0, uint32_t a1, uint32_t a2, uint32_t a3, uint32_t b0, uint32_t b1) {
  asm("mma.sync.aligned.m16n8k16.row.col.f32.bf16.bf16.f32 {%0,%1,%2,%3}, {%4,%5,%6,%7}, {%8,%9}, {%0,%1,%2,%3};"
    : "+f"(d[0]), "+f"(d[1]), "+f"(d[2]), "+f"(d[3]) : "r"(a0), "r"(a1), "r"(a2), "r"(a3), "r"(b0), "r"(b1));
}
__device__ __forceinline__ uint4 ldg128_nc(const void* p) {
  uint4 v; asm volatile("ld.global.nc.L1::no_allocate.v4.u32 {%0,%1,%2,%3}, [%4];" : "=r"(v.x), "=r"(v.y), "=r"(v.z), "=r"(v.w) : "l"(p)); return v;
}
__device__ __forceinline__ void sts128(uint32_t a, uint4 v) {
  asm volatile("st.shared.v4.u32 [%0], {%1,%2,%3,%4};" :: "r"(a), "r"(v.x), "r"(v.y), "r"(v.z), "r"(v.w) : "memory");
}
__device__ __forceinline__ void sts32(uint32_t a, uint32_t v) { asm volatile("st.shared.u32 [%0], %1;" :: "r"(a), "r"(v) : "memory"); }
__device__ __forceinline__ void stsm4(uint32_t a, uint32_t r0, uint32_t r1, uint32_t r2, uint32_t r3) {
  asm volatile("stmatrix.sync.aligned.m8n8.x4.shared.b16 [%0], {%1,%2,%3,%4};" :: "r"(a), "r"(r0), "r"(r1), "r"(r2), "r"(r3) : "memory");
}
__device__ __forceinline__ void named_bar(int id, int n) { asm volatile("bar.sync %0, %1;" :: "r"(id), "r"(n) : "memory"); }
__device__ __forceinline__ void named_arrive(int id, int n) { asm volatile("bar.arrive %0, %1;" :: "r"(id), "r"(n) : "memory"); }

__device__ __forceinline__ uint64_t mk_desc(uint32_t addr, uint32_t lbo, uint32_t sbo, uint32_t swz) {
  uint64_t d = (uint64_t)((addr & 0x3FFFF) >> 4) | ((uint64_t)(lbo >> 4) << 16) | ((uint64_t)(sbo >> 4) << 32) | ((uint64_t)swz << 62);
  return d;
}

template <int SD, int OB> __device__ __forceinline__ void wgmma_rs_n64(float (&d)[32], uint32_t a0, uint32_t a1, uint32_t a2, uint32_t a3, uint64_t db) {
  asm volatile("{\n.reg .b64 db;\nadd.s64 db, %36, %38;\n"
    "wgmma.mma_async.sync.aligned.m64n64k16.f32.bf16.bf16 {%0, %1, %2, %3, %4, %5, %6, %7, %8, %9, %10, %11, %12, %13, %14, %15, %16, %17, %18, %19, %20, %21, %22, %23, %24, %25, %26, %27, %28, %29, %30, %31}, {%32, %33, %34, %35}, db, %37, 1, 1, 1;\n}\n"
    : "+f"(d[0]), "+f"(d[1]), "+f"(d[2]), "+f"(d[3]), "+f"(d[4]), "+f"(d[5]), "+f"(d[6]), "+f"(d[7]), "+f"(d[8]), "+f"(d[9]), "+f"(d[10]), "+f"(d[11]), "+f"(d[12]), "+f"(d[13]), "+f"(d[14]), "+f"(d[15]), "+f"(d[16]), "+f"(d[17]), "+f"(d[18]), "+f"(d[19]), "+f"(d[20]), "+f"(d[21]), "+f"(d[22]), "+f"(d[23]), "+f"(d[24]), "+f"(d[25]), "+f"(d[26]), "+f"(d[27]), "+f"(d[28]), "+f"(d[29]), "+f"(d[30]), "+f"(d[31])
    : "r"(a0), "r"(a1), "r"(a2), "r"(a3), "l"(db), "n"(SD), "n"(OB));
}
template <int SD, int OB> __device__ __forceinline__ void wgmma_rs_n96(float (&d)[48], uint32_t a0, uint32_t a1, uint32_t a2, uint32_t a3, uint64_t db) {
  asm volatile("{\n.reg .b64 db;\nadd.s64 db, %52, %54;\n"
    "wgmma.mma_async.sync.aligned.m64n96k16.f32.bf16.bf16 {%0, %1, %2, %3, %4, %5, %6, %7, %8, %9, %10, %11, %12, %13, %14, %15, %16, %17, %18, %19, %20, %21, %22, %23, %24, %25, %26, %27, %28, %29, %30, %31, %32, %33, %34, %35, %36, %37, %38, %39, %40, %41, %42, %43, %44, %45, %46, %47}, {%48, %49, %50, %51}, db, %53, 1, 1, 1;\n}\n"
    : "+f"(d[0]), "+f"(d[1]), "+f"(d[2]), "+f"(d[3]), "+f"(d[4]), "+f"(d[5]), "+f"(d[6]), "+f"(d[7]), "+f"(d[8]), "+f"(d[9]), "+f"(d[10]), "+f"(d[11]), "+f"(d[12]), "+f"(d[13]), "+f"(d[14]), "+f"(d[15]), "+f"(d[16]), "+f"(d[17]), "+f"(d[18]), "+f"(d[19]), "+f"(d[20]), "+f"(d[21]), "+f"(d[22]), "+f"(d[23]), "+f"(d[24]), "+f"(d[25]), "+f"(d[26]), "+f"(d[27]), "+f"(d[28]), "+f"(d[29]), "+f"(d[30]), "+f"(d[31]), "+f"(d[32]), "+f"(d[33]), "+f"(d[34]), "+f"(d[35]), "+f"(d[36]), "+f"(d[37]), "+f"(d[38]), "+f"(d[39]), "+f"(d[40]), "+f"(d[41]), "+f"(d[42]), "+f"(d[43]), "+f"(d[44]), "+f"(d[45]), "+f"(d[46]), "+f"(d[47])
    : "r"(a0), "r"(a1), "r"(a2), "r"(a3), "l"(db), "n"(SD), "n"(OB));
}
template <int OA, int OB> __device__ __forceinline__ void wgmma_ts_n96(float (&d)[48], uint64_t da, uint64_t db) {
  asm volatile("{\n.reg .b64 da, db;\nadd.s64 da, %48, %50;\nadd.s64 db, %49, %51;\n"
    "wgmma.mma_async.sync.aligned.m64n96k16.f32.bf16.bf16 {%0, %1, %2, %3, %4, %5, %6, %7, %8, %9, %10, %11, %12, %13, %14, %15, %16, %17, %18, %19, %20, %21, %22, %23, %24, %25, %26, %27, %28, %29, %30, %31, %32, %33, %34, %35, %36, %37, %38, %39, %40, %41, %42, %43, %44, %45, %46, %47}, da, db, 1, 1, 1, 1, 1;\n}\n"
    : "+f"(d[0]), "+f"(d[1]), "+f"(d[2]), "+f"(d[3]), "+f"(d[4]), "+f"(d[5]), "+f"(d[6]), "+f"(d[7]), "+f"(d[8]), "+f"(d[9]), "+f"(d[10]), "+f"(d[11]), "+f"(d[12]), "+f"(d[13]), "+f"(d[14]), "+f"(d[15]), "+f"(d[16]), "+f"(d[17]), "+f"(d[18]), "+f"(d[19]), "+f"(d[20]), "+f"(d[21]), "+f"(d[22]), "+f"(d[23]), "+f"(d[24]), "+f"(d[25]), "+f"(d[26]), "+f"(d[27]), "+f"(d[28]), "+f"(d[29]), "+f"(d[30]), "+f"(d[31]), "+f"(d[32]), "+f"(d[33]), "+f"(d[34]), "+f"(d[35]), "+f"(d[36]), "+f"(d[37]), "+f"(d[38]), "+f"(d[39]), "+f"(d[40]), "+f"(d[41]), "+f"(d[42]), "+f"(d[43]), "+f"(d[44]), "+f"(d[45]), "+f"(d[46]), "+f"(d[47])
    : "l"(da), "l"(db), "n"(OA), "n"(OB));
}


template <int I, int N, class F> __device__ __forceinline__ void sfor(F&& f) {
  if constexpr (I < N) { f(std::integral_constant<int, I>()); sfor<I + 1, N>(f); }
}

struct Params {
  const __nv_bfloat16* x; const __nv_bfloat16* wqkv; const __nv_bfloat16* wo; const __nv_bfloat16* w1;
  const __nv_bfloat16* b1; const __nv_bfloat16* w2; const __nv_bfloat16* b2; __nv_bfloat16* out;
  uint64_t zero[12];
};
struct Maps { CUtensorMap x, wq64, wq96, w1, w2, wo, b2, out, qs, qld, kvld; };

__device__ __forceinline__ void ld_win(uint32_t a, uint32_t (&v)[10]) {
#pragma unroll
  for (int u = 0; u < 5; u++) { const uint2 t = lds64(a + u * 8); v[2 * u] = t.x; v[2 * u + 1] = t.y; }
}
__device__ __forceinline__ void attn_task(int i, int t, int lane, uint32_t sb) {
  const uint32_t qb = sb + O_OFF + (t & 1) * 10240 + (t >> 1) * 2304 + lane * 8;
  const uint32_t kb = sb + KST(t) + lane * 8, vb = sb + VST(t) + lane * 8;
  float lg[2][8];
#pragma unroll
  for (int w = 0; w < 8; w++) { lg[0][w] = 0.f; lg[1][w] = 0.f; }
  uint32_t nx[10]; uint2 nq = lds64(qb);
  ld_win(kb, nx);
#pragma unroll
  for (int e = 0; e < 9; e++) {
    uint32_t kk[10];
#pragma unroll
    for (int u = 0; u < 10; u++) kk[u] = nx[u];
    const uint2 q2 = nq;
    if (e < 8) { nq = lds64(qb + (e + 1) * 256); ld_win(kb + (e + 1) * 288, nx); }
    const float q0l = bf_lo(q2.x), q0h = bf_hi(q2.x), q1l = bf_lo(q2.y), q1h = bf_hi(q2.y);
#pragma unroll
    for (int u = 1; u < 10; u++) {
      const float kl = bf_lo(kk[u]), kh = bf_hi(kk[u]);
      if (u <= 8) lg[0][8 - u] = fmaf(q0l, kl, fmaf(q0h, kh, lg[0][8 - u]));
      if (u >= 2) lg[1][9 - u] = fmaf(q1l, kl, fmaf(q1h, kh, lg[1][9 - u]));
    }
  }
  ld_win(vb, nx);
  const float sc = 0.23570226039551584f * 1.4426950408889634f;
  const int p0 = 64 * i + 2 * lane;
#pragma unroll
  for (int a = 0; a < 2; a++) {
    if (i == 0) {
#pragma unroll
      for (int w = 1; w < 8; w++) if (p0 + a - w < 0) lg[a][w] = -1e9f * 4.242640687119285f;
    }
    float m = lg[a][0];
#pragma unroll
    for (int w = 1; w < 8; w++) m = fmaxf(m, lg[a][w]);
    m *= -sc;
    float s = 0.f;
#pragma unroll
    for (int w = 0; w < 8; w++) { lg[a][w] = ex2(fmaf(lg[a][w], sc, m)); s += lg[a][w]; }
    const float inv = __fdividef(1.0f, s);
#pragma unroll
    for (int w = 0; w < 8; w++) lg[a][w] *= inv;
  }
  __syncwarp();
  const uint32_t ob = sb + O_OFF + (t & 1) * 10240 + (lane & 3) * 4;
  uint32_t pp[2][8];
#pragma unroll
  for (int w = 0; w < 8; w++) { pp[0][w] = pack_bf16(lg[0][w], lg[0][w]); pp[1][w] = pack_bf16(lg[1][w], lg[1][w]); }
#pragma unroll
  for (int e = 0; e < 9; e++) {
    uint32_t vv[10];
#pragma unroll
    for (int u = 0; u < 10; u++) vv[u] = nx[u];
    if (e < 8) ld_win(vb + (e + 1) * 288, nx);
    uint32_t oa[2], oc[2];
#pragma unroll
    for (int a = 0; a < 2; a++) {
      oa[a] = bf2_mul(pp[a][7], vv[1 + a]); oc[a] = bf2_mul(pp[a][3], vv[5 + a]);
#pragma unroll
      for (int u = 1; u < 4; u++) { oa[a] = bf2_fma(pp[a][7 - u], vv[1 + a + u], oa[a]); oc[a] = bf2_fma(pp[a][3 - u], vv[5 + a + u], oc[a]); }
      oa[a] = bf2_add(oa[a], oc[a]);
    }
    const uint32_t c = 18 * (t >> 1) + 2 * e;
    sts32(ob + c * 128 + ((((uint32_t)lane >> 2) ^ (c & 7)) << 4), __byte_perm(oa[0], oa[1], 0x5410));
    sts32(ob + (c + 1) * 128 + ((((uint32_t)lane >> 2) ^ ((c + 1) & 7)) << 4), __byte_perm(oa[0], oa[1], 0x7632));
  }
}
__device__ __forceinline__ void stage_round(const Maps& tm, uint32_t sb, int i, int j, int r) {
  const uint32_t b = sb + BAR_OFF + 8 * (B_STG + r);
  mbar_expect(b, (r < 2 ? 3 : 2) * (2304 + 2 * 2592));
#pragma unroll 1
  for (int t = 3 * r; t < 3 * r + 3 && t < 8; t++) {
    const int cp = 36 * j + 9 * (t >> 1), par = t & 1;
    tma3d(sb + KST(t), &tm.kvld, 64 * i - 8, par, 288 + cp, b);
    tma3d(sb + O_OFF + par * 10240 + (t >> 1) * 2304, &tm.qld, 64 * i, par, cp, b);
    tma3d(sb + VST(t), &tm.kvld, 64 * i - 8, par, 576 + cp, b);
  }
}

__global__ void __cluster_dims__(2, 1, 1) __launch_bounds__(384, 1)
fused_kernel(const __grid_constant__ Maps tm, const Params p) {
  extern __shared__ __align__(1024) uint8_t smem[];
  const uint32_t sb = s2u(smem);
  const uint32_t bar = sb + BAR_OFF;
  const int j = blockIdx.x >> 4, i = blockIdx.x & 15;
  if (threadIdx.x < 32) {
    if (elect_one()) {
#pragma unroll
      for (int b = 0; b < 9; b++) {
        mbar_init(bar + 8 * (B_X + b), 1);
        mbar_expect(bar + 8 * (B_X + b), 16384);
        tma4d(sb + b * 16384, &tm.x, 0, 64 * i, 0, b, bar + 8 * (B_X + b));
      }
      asm volatile("fence.mbarrier_init.release.cluster;" ::: "memory");
    }
  }
  const int warp = __shfl_sync(0xffffffff, threadIdx.x >> 5, 0);
  const int lane = threadIdx.x & 31;
  const int rank = blockIdx.x & 1;
  const int qc0 = 224 * j;

  if (warp == 9 && elect_one()) {
#pragma unroll
    for (int b = 0; b < B_X; b++)
      mbar_init(bar + 8 * b, (b >= E1 && b < B_B1) ? 16 : ((b >= B_QS && b < B_O) ? 8 : ((b >= B_O && b < B_STG) ? 3 : ((b == B_RED || b == B_RED + 1) ? 4 : 1))));
    asm volatile("fence.mbarrier_init.release.cluster;" ::: "memory");
  }
  __syncwarp();

  if (warp >= 8) {
    asm volatile("setmaxnreg.dec.sync.aligned.u32 56;");
    if (warp == 8) {
      asm volatile("barrier.cluster.arrive.relaxed.aligned;" ::: "memory");
      asm volatile("barrier.cluster.wait.aligned;" ::: "memory");
      if (elect_one()) {
        int slot = 0; uint32_t ph = 1;
        mbar_wait(bar + 8 * (B_X + 3), 0);
        const uint32_t ring = sb + RING_OFF + rank * 6144;
#define PRODUCE(MAP, C1, C2) do { \
          mbar_wait(bar + 8 * (E1 + slot), ph); \
          mbar_expect(bar + 8 * (F1 + slot), 12288); \
          tma3d_mc(ring + slot * 12288, MAP, 0, C1, C2, bar + 8 * (F1 + slot)); \
          if (++slot == 6) { slot = 0; ph ^= 1; } } while (0)
        const uint8_t* pf1 = (const uint8_t*)(p.w1 + (size_t)(36 * i) * 4608 + 576 * j);
#define PF3() do { l2_prefetch(pf1, 1152); l2_prefetch(pf1 + 9216, 1152); l2_prefetch(pf1 + 18432, 1152); pf1 += 27648; } while (0)
#pragma unroll 1
        for (int s = 0; s < 9; s++) {
          PRODUCE(&tm.wq96, 64 * s + 32 * rank, qc0 >> 5);
          if (s >= 6) { PF3(); }
        }
#pragma unroll 1
        for (int s = 0; s < 12; s++) {
          if (j == 7 && s >= 6) {
            mbar_wait(bar + 8 * (E1 + slot), ph);
            mbar_arrive(bar + 8 * (F1 + slot));
            if (++slot == 6) { slot = 0; ph ^= 1; }
          } else PRODUCE(&tm.wq64, 96 * (s % 6) + 48 * rank, (qc0 >> 5) + (s >= 6 ? 5 : 3));
          if (s < 9) { PF3(); }
        }
        const uint8_t* pf = (const uint8_t*)(p.w2 + (size_t)(576 * j + 36 * i) * 576);
#pragma unroll 1
        for (int c = 0; c < 6; c++) {
#pragma unroll 1
          for (int s = 0; s < 9; s++) {
            PRODUCE(&tm.w1, 64 * s + 32 * rank, 18 * j + 3 * c);
            if (c < 4) { l2_prefetch(pf, 1152); pf += 1152; }
            else if (c == 4) l2_prefetch((const uint8_t*)(p.wo + (size_t)(72 * j) * 576) + (9 * i + s) * 576, 576);
          }
        }
        int pc = j % 6;
#pragma unroll 1
        for (int c = 0; c < 6; c++) {
#pragma unroll
          for (int k = 0; k < 10; k++) {
            if (c > 0) mbar_wait(bar + 8 * (EG + k), (c - 1) & 1);
            else if (k < 6) mbar_wait(bar + 8 * (E1 + (3 + k) % 6), k < 3 ? 1 : 0);
            else if (k == 6) mbar_wait(bar + 8 * B_HFREE, 0);
            const uint32_t dst = sb + G2S(k) + rank * 6144, fb = bar + 8 * (FG + k);
            if (k < 9) {
              mbar_expect(fb, 12288);
              tma3d_mc(dst, &tm.w2, 0, 576 * j + 64 * k + 32 * rank, 3 * pc, fb);
            } else {
              mbar_expect(fb, 18432);
              tma3d_mc(dst, &tm.wo, 0, 72 * j + 32 * rank, 3 * pc, fb);
              tma3d_mc(dst + 3072, &tm.wo, 0, 72 * j + 32 * rank + 16, 3 * pc, fb);
              if (rank == 0) tma3d_mc(dst + 12288, &tm.wo, 0, 72 * j + 64, 3 * pc, fb);
              else tma3d_mc(dst + 9216, &tm.b2, 0, 0, 3 * pc, fb);
            }
          }
          if (++pc == 6) pc = 0;
        }
#undef PRODUCE
      }
    } else {
      const int ht = threadIdx.x - 288;
      if (sb & 1023) __trap();
      asm volatile("barrier.cluster.arrive.relaxed.aligned;" ::: "memory");
      uint32_t b1v[3];
#pragma unroll
      for (int u = 0; u < 3; u++) {
        const int idx = ht + 96 * u, ps = idx / 48, qq = (idx % 48) / 12, t = idx % 12;
        b1v[u] = __ldg((const uint32_t*)p.b1 + 288 * j + 48 * ps + 4 * t + qq);
      }
      asm volatile("barrier.cluster.wait.aligned;" ::: "memory");
#pragma unroll
      for (int u = 0; u < 3; u++) sts32(sb + B1_OFF + (ht + 96 * u) * 4, b1v[u]);
      mbar_wait(bar + 8 * (B_X + 5), 0);
      pf_rows<12, 192>(p.wqkv + (size_t)(384 + 12 * i) * 1728 + qc0, 3456, ht);
      pf_rows<36, 256>(p.wqkv + (size_t)(36 * i) * 1728 + min(qc0 + 96, 1600), 3456, ht);
      mbar_wait(bar + 8 * (B_X + 8), 0);
      if (ht < 72) {
        const size_t e0 = (size_t)(128 * i + 16 * j) * 576 + ht * 8;
#pragma unroll
        for (int hf = 0; hf < 2; hf++) {
          uint4 xv[8];
#pragma unroll
          for (int r = 0; r < 8; r++) xv[r] = ldg128_nc(p.x + e0 + (8 * hf + r) * 576);
#pragma unroll
          for (int r = 0; r < 8; r++)
            *(uint4*)(p.out + e0 + (8 * hf + r) * 576) = xv[r];
        }
      }
      named_bar(3, 96);
      if (ht == 0) {
#pragma unroll 1
        for (int n = 0; n < (j == 7 ? 5 : 7); n++) {
          if (n == 0 || n == 3 || n == 5) mbar_wait(bar + 8 * (B_QS + (n >> 1)), 0);
#pragma unroll 1
          for (int hf = 0; hf < 2; hf++) {
            tma_st4d(&tm.qs, 0, (qc0 >> 1) + 16 * n, 4 * i, hf, sb + H_OFF + n * 8192 + hf * 4096);
            bulk_commit();
            if (n < 5) __nanosleep(QPACE);
          }
          if (n == 2) {
            asm volatile("cp.async.bulk.wait_group.read 0;" ::: "memory");
            mbar_arrive(bar + 8 * B_B1);
          }
        }
        asm volatile("cp.async.bulk.wait_group 0;" ::: "memory");
        mbar_arrive(bar + 8 * B_B2);
        asm volatile("fence.proxy.async.global;" ::: "memory");
        asm volatile("red.release.gpu.global.add.u32 [%0], 1;" :: "l"(&g_cnt[i * 32]) : "memory");
        unsigned int v; int n = 0;
        do { asm volatile("ld.acquire.gpu.global.u32 %0, [%1];" : "=r"(v) : "l"(&g_cnt[i * 32]) : "memory"); if (++n > 20000000) __trap(); } while (v < 8);
        if (i > 0) {
          do { asm volatile("ld.acquire.gpu.global.u32 %0, [%1];" : "=r"(v) : "l"(&g_cnt[(i - 1) * 32]) : "memory"); if (++n > 20000000) __trap(); } while (v < 8);
        }
        asm volatile("fence.proxy.async.global;" ::: "memory");
        stage_round(tm, sb, i, j, 0);
      }
      __syncwarp();
#pragma unroll 1
      for (int r = 0; r < 3; r++) {
        const int t = 3 * r + warp - 9;
        if (t < 8) {
          mbar_wait(bar + 8 * (B_STG + r), 0);
          if (warp == 11 && elect_one()) stage_round(tm, sb, i, j, r + 1);
          __syncwarp();
          attn_task(i, t, lane, sb);
        } else {
#pragma unroll
          for (int e = 0; e < 4; e++) {
            const uint32_t z = (!(e & 1) && lane < 8) ? 0x3e003e00u : 0u;
            sts128(sb + O_OFF + (e >> 1) * 10240 + 9216 + ((e & 1) * 32 + lane) * 16, make_uint4(z, z, z, z));
          }
        }
        if (r == 2) asm volatile("fence.proxy.async.shared::cta;" ::: "memory");
        __syncwarp();
        if (lane == 0) mbar_arrive(bar + 8 * (B_O + r));
      }
      if (ht == 0) {
        if (atomicAdd(&g_used[i * 32], 1) == (i == 15 ? 7u : 15u)) { g_cnt[i * 32] = 0; g_used[i * 32] = 0; }
        if (i > 0 && atomicAdd(&g_used[(i - 1) * 32], 1) == 15u) { g_cnt[(i - 1) * 32] = 0; g_used[(i - 1) * 32] = 0; }
      }
      __syncwarp();
      if (warp == 10 && elect_one()) {
        int pc = j % 6;
#pragma unroll 1
        for (int ps = 0; ps < 5; ps++) {
#pragma unroll 1
          for (int wd = 0; wd < 8; wd++) {
            if ((wd & 3) == 0) mbar_wait(bar + 8 * (B_RED + (wd >> 2)), ps & 1);
            tma_red4d(&tm.out, 0, wd >> 2, 64 * i + 16 * (wd & 3), 3 * pc, sb + H_OFF + ((ps + 1) & 1) * HSLOT + wd * 3072);
            bulk_commit();
            asm volatile("cp.async.bulk.wait_group.read 0;" ::: "memory");
            __nanosleep(RPACE);
          }
          mbar_arrive(bar + 8 * B_RFREE);
          if (++pc == 6) pc = 0;
        }
      }
    }
  } else {
    asm volatile("barrier.cluster.arrive.relaxed.aligned;" ::: "memory");
    asm volatile("barrier.cluster.wait.aligned;" ::: "memory");
    asm volatile("setmaxnreg.inc.sync.aligned.u32 224;");
    const int g = warp >> 2, w = warp & 3, r8 = lane >> 2, q = lane & 3;
    uint32_t a[144];
    uint32_t nh0, nm0, nh1, nm1;
    {
      const uint32_t lrow = sb + g * 8192 + (16 * w + (lane & 15)) * 128;
      const uint32_t lx = lane & 7, lh = lane >> 4;
      float su[2][4] = {}, qa[2][4] = {}, qb[2][4] = {}, qc[2][4] = {}, qd[2][4] = {};
      const uint32_t ones = 0x3f803f80u;
#pragma unroll
      for (int kb = 0; kb < 9; kb++) {
        mbar_wait_c(bar + 8 * (B_X + kb), 0);
#pragma unroll
        for (int k = 4 * kb; k < 4 * kb + 4; k++)
          ldsm4(lrow + kb * 16384 + (((2 * (k & 3) + lh) ^ lx) << 4), a[4 * k], a[4 * k + 1], a[4 * k + 2], a[4 * k + 3]);
#pragma unroll
        for (int k = 4 * kb; k < 4 * kb + 4; k++) {
          mma16816(su[k & 1], a[4 * k], a[4 * k + 1], a[4 * k + 2], a[4 * k + 3], ones, ones);
          mma16816((k & 2) ? qc[k & 1] : qa[k & 1], a[4 * k], a[4 * k + 1], a[4 * k + 2], a[4 * k + 3], a[4 * k], a[4 * k + 2]);
          mma16816((k & 2) ? qd[k & 1] : qb[k & 1], a[4 * k], a[4 * k + 1], a[4 * k + 2], a[4 * k + 3], a[4 * k + 1], a[4 * k + 3]);
        }
        asm volatile("" : "+f"(su[0][0]), "+f"(qa[0][0]), "+f"(qb[0][0]), "+f"(qc[0][0]), "+f"(qd[0][0]),
                          "+f"(su[1][0]), "+f"(qa[1][0]), "+f"(qb[1][0]), "+f"(qc[1][0]), "+f"(qd[1][0]) :: "memory");
      }
      float q0 = (r8 & 1) ? (qa[0][1] + qc[0][1]) + (qa[1][1] + qc[1][1]) : (qa[0][0] + qc[0][0]) + (qa[1][0] + qc[1][0]);
      float q1 = (r8 & 1) ? (qb[0][3] + qd[0][3]) + (qb[1][3] + qd[1][3]) : (qb[0][2] + qd[0][2]) + (qb[1][2] + qd[1][2]);
      const int src = (lane & ~3) | (r8 >> 1);
      q0 = __shfl_sync(0xffffffff, q0, src); q1 = __shfl_sync(0xffffffff, q1, src);
      const float m0 = (su[0][0] + su[1][0]) * (1.0f / 576.0f), m1 = (su[0][2] + su[1][2]) * (1.0f / 576.0f);
      const uint32_t vb = pack_bf16(fmaxf(q0 * (1.0f / 576.0f) - m0 * m0, 0.f), fmaxf(q1 * (1.0f / 576.0f) - m1 * m1, 0.f));
      const uint32_t eb = pack_bf16(bf_lo(vb) + 1e-5f, bf_hi(vb) + 1e-5f);
      const uint32_t sd = pack_bf16(sqrt_fast(bf_lo(eb)), sqrt_fast(bf_hi(eb))), mb = pack_bf16(m0, m1);
      const float rs0 = __fdividef(1.0f, bf_lo(sd)), rs1 = __fdividef(1.0f, bf_hi(sd));
      nh0 = pack_bf16(rs0, rs0); nm0 = __byte_perm(mb, 0, 0x1010);
      nh1 = pack_bf16(rs1, rs1); nm1 = __byte_perm(mb, 0, 0x3232);
    }
#define NORMALIZE(U0, U1) \
    _Pragma("unroll") for (int u = U0; u < U1; u += 2) { \
      a[u] = bf2_mul(bf2_sub(a[u], nm0), nh0); a[u + 1] = bf2_mul(bf2_sub(a[u + 1], nm1), nh1); }
    NORMALIZE(0, 16);

    const uint32_t rbase = mapa(bar, lane & 1);
    bool rel = lane < 2;
    const uint32_t pl = sb + H_OFF + warp * 1024 + lane * 16;
    const uint64_t dW96 = mk_desc(sb, 2048, 512, 2), dW64 = mk_desc(sb, 3072, 512, 2);
    uint32_t tok;
    uint32_t pk[16];
#define STAGE(NK, MMA, NFB, NPAR, PEB, LASTK, HOOK) \
      wg_arrive(); \
      sfor<0, NK>([&](auto KK) { constexpr int kk = decltype(KK)::value; MMA; if (kk == NK - 3 && !(LASTK)) tok = mbar_peek(bar + 8 * (NFB), NPAR); }); \
      wg_commit(); \
      if ((LASTK) && g == 0) named_arrive(4, 256); \
      HOOK \
      if ((PEB) >= 0) { wg_wait<1>(); if (rel) arrive_cluster(rbase + 8 * ((PEB) < 0 ? 0 : (PEB))); }
#define NEXT(NFB, NPAR) if (!tok) mbar_wait_c(bar + 8 * (NFB), NPAR);
#define MMA96(ADDR) do { constexpr int t = 4 * (4 * k + kk); \
      wgmma_rs_n96<(k + kk > 0), (((ADDR) + (kk >> 1) * 6144 + (kk & 1) * 1024) >> 4)>(acc, a[t], a[t + 1], a[t + 2], a[t + 3], dB[k / 6]); } while (0)
#define MMA64(ADDR) do { constexpr int t = 4 * (6 * k + kk); \
      wgmma_rs_n64<(k + kk > 0), (((ADDR) + (kk / 3) * 6144 + (kk % 3) * 1024) >> 4)>(acc, a[t], a[t + 1], a[t + 2], a[t + 3], dB); } while (0)
#define FORK(N) sfor<0, N>([&](auto KC) { constexpr int k = decltype(KC)::value;
#define ENDK });
#define PUBLISH(B) do { asm volatile("fence.proxy.async.shared::cta;" ::: "memory"); __syncwarp(); if (lane == 0) mbar_arrive(bar + 8 * (B)); } while (0)
#define QKV_STORE(PIECE) do { const uint32_t st = qst + (PIECE) * 8192; \
      _Pragma("unroll") for (int u = 0; u < 16; u++) sts32(st + (u >> 3) * 8192 + ((u >> 1) & 3) * 256 + (u & 1) * 32, pk[u]); } while (0)
#define RELOAD(U0, U1) \
      _Pragma("unroll") for (int u = U0; u < U1; u++) { \
        const uint4 v = lds128(pl + (u / 6) * HSLOT + ((u % 6) >> 1) * 8192 + (u & 1) * 512); \
        a[4 * u] = v.x; a[4 * u + 1] = v.y; a[4 * u + 2] = v.z; a[4 * u + 3] = v.w; }
    const uint32_t qst = sb + H_OFF + warp * 1024 + q * 64 + r8 * 4;

    {
      float acc[48];
      const uint64_t dB[2] = {dW96 + p.zero[0], dW96 + p.zero[1]};
      mbar_wait_c(bar + 8 * F1, 0);
      FORK(9)
        if (k == 9 - LAG && g == 1) named_bar(4, 256);
        STAGE(4, MMA96(RING_OFF + (k % 6) * 12288), F1 + (k + 1) % 6, ((k + 1) / 6) & 1, k > 0 ? E1 + (k + 5) % 6 : -1, k == 8, );
        if constexpr (k < 8) {
#pragma unroll
          for (int u = 16 * k + 16; u < 16 * k + 32; u++) asm volatile("" : "+r"(a[u]) :: "memory");
          NORMALIZE(16 * k + 16, 16 * k + 32);
          NEXT(F1 + (k + 1) % 6, ((k + 1) / 6) & 1);
        }
      ENDK
      wg_wait<0>();
      fence_regs(acc);
      if (rel) arrive_cluster(rbase + 8 * (E1 + 2));
      tok = mbar_peek(bar + 8 * (F1 + 3), 1);
#pragma unroll
      for (int t = 0; t < 4; t++) {
        sts32(qst + t * 256, pack_bf16(acc[4 * t], acc[4 * t + 1]));
        sts32(qst + t * 256 + 32, pack_bf16(acc[4 * t + 2], acc[4 * t + 3]));
      }
#pragma unroll
      for (int u = 0; u < 16; u++) pk[u] = pack_bf16(acc[16 + 2 * u], acc[17 + 2 * u]);
      NEXT(F1 + 3, 1);
    }
#pragma unroll 1
    for (int d = 0; d < 2; d++) {
      if (j == 7 && d == 1) {
        QKV_STORE(3);
        PUBLISH(B_QS + 1);
#pragma unroll 1
        for (int k = 0; k < 6; k++) {
          const int sl = (3 + k) % 6;
          mbar_wait_c(bar + 8 * (F1 + sl), k < 3 ? 0 : 1);
          if (rel) arrive_cluster(rbase + 8 * (E1 + sl));
        }
        mbar_wait_c(bar + 8 * (F1 + 3), 1);
        break;
      }
      float acc[32];
      const uint64_t dB = dW64 + (p.zero[2] << d);
      const uint32_t par[2] = {(uint32_t)d, (uint32_t)d ^ 1u};
      FORK(6)
        if (k == 6 - LAG && g == 1) named_bar(4, 256);
        STAGE(6, MMA64(RING_OFF + ((3 + k) % 6) * 12288), F1 + (4 + k) % 6, par[(1 + (4 + k) / 6) & 1], k > 0 ? E1 + (2 + k) % 6 : -1, k == 5, );
        if (k == 0) QKV_STORE(1 + 2 * d);
        if (k == 1) PUBLISH(B_QS + d);
        if (k < 5) NEXT(F1 + (4 + k) % 6, par[(1 + (4 + k) / 6) & 1]);
      ENDK
      wg_wait<0>();
      fence_regs(acc);
      if (rel) arrive_cluster(rbase + 8 * (E1 + 2));
      tok = mbar_peek(bar + 8 * (F1 + 3), par[0]);
#pragma unroll
      for (int u = 0; u < 16; u++) pk[u] = pack_bf16(acc[2 * u], acc[2 * u + 1]);
      NEXT(F1 + 3, par[0]);
    }
    auto hidden = [&](auto OFFC, auto LASTC, const int d) {
      constexpr int OFF = decltype(OFFC)::value;
      constexpr bool LASTP = decltype(LASTC)::value;
      const int c = 2 * d + (OFF == 0);
      float acc[48];
      constexpr int ZI = LASTP ? 7 : (OFF ? 3 : 5);
      const uint64_t dB[2] = {dW96 + (p.zero[ZI] << d), dW96 + (p.zero[ZI + 1] << d)};
      const uint32_t par[2] = {(uint32_t)d & 1u, ((uint32_t)d & 1u) ^ 1u};
      FORK(9)
        if (k == 9 - LAG && g == 1) named_bar(4, 256);
        STAGE(4, MMA96(RING_OFF + ((OFF + k) % 6) * 12288), F1 + (OFF + k + 1) % 6, par[(1 + (OFF + k + 1) / 6) & 1], k > 0 ? E1 + (OFF + k + 5) % 6 : -1, k == 8,
               if constexpr (LASTP && k >= 2) { RELOAD(4 * (k - 2), 4 * (k - 1)); });
        if constexpr (LASTP && k == 8) { RELOAD(28, 30); }
        if constexpr (OFF == 3 && k < 2) {
          if (d == 0) { if (k == 0) QKV_STORE(5); else PUBLISH(B_QS + 2); }
        }
        if constexpr (k == DEFK || k == DEFK + 1) {
          if (OFF == 0 || d > 0) {
            constexpr int e = k - DEFK;
            if (e == 0 && c >= 4) mbar_wait_c(bar + 8 * (B_O + c - 4), 0);
            const uint4 v = lds128(sb + B1_OFF + (c - 1) * 192 + q * 48 + 16 + e * 16);
            const uint32_t bb[4] = {v.x, v.y, v.z, v.w};
#pragma unroll
            for (int u = 0; u < 2; u++)
              sts128(pl + (c - 1) * HSLOT + (1 + e) * 8192 + u * 512,
                     make_uint4(bf2_sq(bf2_add_relu(pk[8 * e + 4 * u], bb[2 * u])), bf2_sq(bf2_add_relu(pk[8 * e + 4 * u + 1], bb[2 * u])),
                                bf2_sq(bf2_add_relu(pk[8 * e + 4 * u + 2], bb[2 * u + 1])), bf2_sq(bf2_add_relu(pk[8 * e + 4 * u + 3], bb[2 * u + 1]))));
          }
        }
        if (k == 7 && !LASTP && d == 0) mbar_wait_c(bar + 8 * (OFF == 3 ? B_B1 : B_B2), 0);
        if (k < 8) NEXT(F1 + (OFF + k + 1) % 6, par[(1 + (OFF + k + 1) / 6) & 1]);
      ENDK
      if (LASTP) { __syncwarp(); if (rel) arrive_cluster(rbase + 8 * B_HFREE); }
      const uint4 bv = lds128(sb + B1_OFF + c * 192 + q * 48);
      wg_wait<0>();
      fence_regs(acc);
      if (rel) arrive_cluster(rbase + 8 * (E1 + (OFF + 8) % 6));
      constexpr int NB = LASTP ? FG : F1 + (OFF + 9) % 6;
      const uint32_t np = LASTP ? 0u : par[(1 + (OFF + 9) / 6) & 1];
      tok = mbar_peek(bar + 8 * NB, np);
      if constexpr (LASTP) {
#pragma unroll
        for (int u = 0; u < 24; u++) a[120 + u] = pack_bf16(acc[2 * u], acc[2 * u + 1]);
      } else {
        const uint32_t bb[4] = {bv.x, bv.y, bv.z, bv.w};
#pragma unroll
        for (int u = 0; u < 2; u++)
          sts128(pl + c * HSLOT + u * 512,
                 make_uint4(bf2_sq(bf2_add_relu(pack_bf16(acc[8 * u], acc[8 * u + 1]), bb[2 * u])), bf2_sq(bf2_add_relu(pack_bf16(acc[8 * u + 2], acc[8 * u + 3]), bb[2 * u])),
                            bf2_sq(bf2_add_relu(pack_bf16(acc[8 * u + 4], acc[8 * u + 5]), bb[2 * u + 1])), bf2_sq(bf2_add_relu(pack_bf16(acc[8 * u + 6], acc[8 * u + 7]), bb[2 * u + 1]))));
#pragma unroll
        for (int u = 0; u < 16; u++) pk[u] = pack_bf16(acc[16 + 2 * u], acc[17 + 2 * u]);
      }
      NEXT(NB, np);
    };
#pragma unroll 1
    for (int d = 0; d < 3; d++) {
      hidden(std::integral_constant<int, 3>(), std::false_type(), d);
      if (d == 2) break;
      hidden(std::integral_constant<int, 0>(), std::false_type(), d);
    }
    hidden(std::integral_constant<int, 0>(), std::true_type(), 2);
    {
      const uint64_t dO0 = mk_desc(sb + O_OFF + g * 10240, 1024, 1024, 1), dWo0 = mk_desc(sb + G2S(9), 1024, 512, 2);
      const uint32_t srow = (lane & 7) + ((lane >> 3) & 1) * 8;
      const uint32_t sa = sb + H_OFF + warp * 3072 + srow * 64 + (((lane >> 4) ^ ((srow >> 1) & 3)) << 4);
#pragma unroll 1
      for (int c = 0; c < 6; c++) {
        float acc[48];
        const uint64_t dB0 = dW96 + (p.zero[9] << c);
        const uint64_t dB[2] = {dB0, dB0};
        const uint64_t dO = dO0 + (p.zero[10] << c), dWo = dWo0 + (p.zero[11] << c);
        const uint32_t par = c & 1;
        rel = rel && c < 5;
        FORK(9)
          if (k == 10 - LAG2 && g == 1) named_bar(4, 256);
          STAGE(4, MMA96(G2S(k)), FG + k + 1, par, k > 0 ? EG + k - 1 : -1, false, );
          if (k == 0 && c > 0) {
            if (c > 1) mbar_wait_c(bar + 8 * B_RFREE, par);
            PUBLISH(B_RED + g);
          }
          if constexpr (k >= 1 && k < 4) {
            if (c == 0) {
              const uint4 v = lds128(sb + B1_OFF + 5 * 192 + q * 48 + (k - 1) * 16);
              const uint32_t bb[4] = {v.x, v.y, v.z, v.w};
#pragma unroll
              for (int u = 0; u < 8; u++) a[112 + 8 * k + u] = bf2_sq(bf2_add_relu(a[112 + 8 * k + u], bb[u >> 1]));
            }
          }
          if (k == 7 && c == 0) mbar_wait_c(bar + 8 * (B_O + 2), 0);
          NEXT(FG + k + 1, par);
        ENDK
        STAGE(5, (wgmma_ts_n96<128 * kk, 192 * kk>(acc, dO, kk < 4 ? dWo : dWo + ((uint64_t)((3072 - 512) >> 4) << 32))), 0, 0, EG + 8, true, );
        wg_wait<0>();
        fence_regs(acc);
        if (rel) arrive_cluster(rbase + 8 * (EG + 9));
        tok = c < 5 ? mbar_peek(bar + 8 * FG, par ^ 1) : 1;
        const uint32_t so = sa + (par ^ 1) * HSLOT;
#pragma unroll
        for (int t = 0; t < 6; t++) {
          stsm4((so ^ (32 * (t & 1))) + (t >> 1) * 1024,
                pack_bf16(acc[8 * t], acc[8 * t + 1]), pack_bf16(acc[8 * t + 2], acc[8 * t + 3]),
                pack_bf16(acc[8 * t + 4], acc[8 * t + 5]), pack_bf16(acc[8 * t + 6], acc[8 * t + 7]));
        }
        NEXT(FG, par ^ 1);
      }
      asm volatile("fence.proxy.async.shared::cta;" ::: "memory");
      __syncwarp();
      if (elect_one()) {
        tma_red4d(&tm.out, 0, g, 64 * i + 16 * w, 3 * ((j + 5) % 6), sb + H_OFF + warp * 3072);
        bulk_commit();
        asm volatile("cp.async.bulk.wait_group.read 0;" ::: "memory");
      }
    }
  }
}

typedef CUresult (*EncodeFn)(CUtensorMap*, CUtensorMapDataType, cuuint32_t, void*, const cuuint64_t*, const cuuint64_t*,
                             const cuuint32_t*, const cuuint32_t*, CUtensorMapInterleave, CUtensorMapSwizzle,
                             CUtensorMapL2promotion, CUtensorMapFloatOOBfill);

void make_map(EncodeFn fn, CUtensorMap* tm, CUtensorMapDataType dt, const void* ptr, int rank, const cuuint64_t* dims,
              const cuuint64_t* strides, const cuuint32_t* box, CUtensorMapSwizzle swz) {
  cuuint32_t es[5] = {1, 1, 1, 1, 1};
  fn(tm, dt, rank, const_cast<void*>(ptr), dims, strides, box, es,
     CU_TENSOR_MAP_INTERLEAVE_NONE, swz, CU_TENSOR_MAP_L2_PROMOTION_NONE, CU_TENSOR_MAP_FLOAT_OOB_FILL_NONE);
}

}

extern "C" void kernel_launch(void* const* d_in, const int* in_sizes, int n_in, void* d_out, int out_size) {
  (void)in_sizes; (void)n_in; (void)out_size;
  Params p;
  p.x = (const __nv_bfloat16*)d_in[0];
  p.wqkv = (const __nv_bfloat16*)d_in[1];
  p.wo = (const __nv_bfloat16*)d_in[2];
  p.w1 = (const __nv_bfloat16*)d_in[4];
  p.b1 = (const __nv_bfloat16*)d_in[5];
  p.w2 = (const __nv_bfloat16*)d_in[6];
  p.b2 = (const __nv_bfloat16*)d_in[7];
  p.out = (__nv_bfloat16*)d_out;
  for (int z = 0; z < 12; z++) p.zero[z] = 0;

  void* fnp = nullptr;
  cudaDriverEntryPointQueryResult qr;
  cudaGetDriverEntryPoint("cuTensorMapEncodeTiled", &fnp, cudaEnableDefault, &qr);
  EncodeFn fn = (EncodeFn)fnp;
  void* qkv = nullptr;
  cudaGetSymbolAddress(&qkv, g_qkvT);

  const CUtensorMapDataType BF = CU_TENSOR_MAP_DATA_TYPE_BFLOAT16, U32 = CU_TENSOR_MAP_DATA_TYPE_UINT32;
  const CUtensorMapSwizzle S128 = CU_TENSOR_MAP_SWIZZLE_128B, S64 = CU_TENSOR_MAP_SWIZZLE_64B, S0 = CU_TENSOR_MAP_SWIZZLE_NONE;
  Maps tm;
  { cuuint64_t d[4] = {64, 1024, 2, 9}; cuuint64_t s[3] = {2304, 1152, 128}; cuuint32_t b[4] = {64, 64, 2, 1};
    make_map(fn, &tm.x, BF, p.x, 4, d, s, b, S128); }
  { cuuint64_t d[3] = {32, 576, 54}; cuuint64_t s[2] = {3456, 64};
    cuuint32_t b[3] = {32, 48, 2}; make_map(fn, &tm.wq64, BF, p.wqkv, 3, d, s, b, S64);
    cuuint32_t c[3] = {32, 32, 3}; make_map(fn, &tm.wq96, BF, p.wqkv, 3, d, s, c, S64); }
  { cuuint64_t d[3] = {32, 576, 144}; cuuint64_t s[2] = {9216, 64}; cuuint32_t b[3] = {32, 32, 3};
    make_map(fn, &tm.w1, BF, p.w1, 3, d, s, b, S64); }
  { cuuint64_t d[3] = {32, 4608, 18}; cuuint64_t s[2] = {1152, 64}; cuuint32_t b[3] = {32, 32, 3};
    make_map(fn, &tm.w2, BF, p.w2, 3, d, s, b, S64); }
  { cuuint64_t d[3] = {32, 576, 18}; cuuint64_t s[2] = {1152, 64}; cuuint32_t b[3] = {32, 16, 3};
    make_map(fn, &tm.wo, BF, p.wo, 3, d, s, b, S64);
    cuuint64_t d1[3] = {32, 1, 18}; make_map(fn, &tm.b2, BF, p.b2, 3, d1, s, b, S64); }
  { cuuint64_t d[4] = {32, 2, 1024, 18}; cuuint64_t s[3] = {1152, 2304, 64}; cuuint32_t b[4] = {32, 1, 16, 3};
    make_map(fn, &tm.out, BF, p.out, 4, d, s, b, S64); }
  { cuuint64_t d[3] = {1024, 2, 864}; cuuint64_t s[2] = {4096, 8192};
    cuuint32_t c[3] = {64, 1, 9}; make_map(fn, &tm.qld, U32, qkv, 3, d, s, c, S0);
    cuuint32_t e[3] = {72, 1, 9}; make_map(fn, &tm.kvld, U32, qkv, 3, d, s, e, S0); }

  { cuuint64_t d[4] = {16, 864, 64, 2}; cuuint64_t s[3] = {8192, 64, 4096};
    cuuint32_t b[4] = {16, 16, 4, 1}; make_map(fn, &tm.qs, U32, qkv, 4, d, s, b, S0); }

  cudaFuncSetAttribute(fused_kernel, cudaFuncAttributeMaxDynamicSharedMemorySize, SMEM_BYTES);
  fused_kernel<<<128, 384, SMEM_BYTES>>>(tm, p);
}
```
